```python
import torch

def _softmax(x, axis=-1):
    return torch.softmax(x, dim=axis)

def _gelu(x):
    return torch.nn.functional.gelu(x, approximate='tanh')

def _silu(x):
    return torch.nn.functional.silu(x)

def _sigmoid(x):
    return torch.sigmoid(x)

def _layernorm(x, axis=-1, eps=1e-05):
    m = x.mean(dim=axis, keepdim=True)
    v = x.var(dim=axis, keepdim=True, unbiased=False)
    return (x - m) / torch.sqrt(v + eps)

def _scatter_add(tgt, idx, src, axis=0):
    return tgt.clone().index_add_(axis, idx, src)

def _segment_sum(src, seg, n):
    out = torch.zeros((n,) + src.shape[1:], dtype=src.dtype)
    return out.index_add_(0, seg, src)

def _pad(x, pw):
    flat = tuple((v for pair in reversed(pw) for v in pair))
    return torch.nn.functional.pad(x, flat)
kernel_name = 'standalone__tree_speculative_verify_tree_attention_over_candidate_token_tree__sampling'

def setup_inputs():

    _w = lambda a: (lambda t: t.to(torch.bfloat16) if t.is_floating_point() else t)(torch.as_tensor(a))
    B, Hq, Hkv, T, C, D = (16, 32, 32, 4, 2048, 128)
    tree_mask = torch.zeros((B, T, T), dtype=float)
    for b in range(B):
        parent = torch.zeros(T, dtype=torch.int64)
        for i in range(1, T):
            parent[i] = int(torch.randint(0, i, (1,)).item())
        for i in range(T):
            j = i
            tree_mask[b, i, j] = 1.0
            while j > 0:
                j = parent[j]
                tree_mask[b, i, j] = 1.0
    return {'q': _w((lambda *s: torch.randn(*s, dtype=torch.bfloat16) * 0.8)(B, Hq, T, D)), 'k_cache': _w((lambda *s: torch.randn(*s, dtype=torch.bfloat16) * 0.8)(B, Hkv, C, D)), 'v_cache': _w((lambda *s: torch.randn(*s, dtype=torch.bfloat16) * 0.05)(B, Hkv, C, D)), 'k_tree': _w((lambda *s: torch.randn(*s, dtype=torch.bfloat16) * 0.8)(B, Hkv, T, D)), 'v_tree': _w((lambda *s: torch.randn(*s, dtype=torch.bfloat16) * 0.05)(B, Hkv, T, D)), 'tree_mask': _w(tree_mask)}

def reference(q, k_cache, v_cache, k_tree, v_tree, tree_mask):
    B, Hq, T, D = q.shape
    Hkv, C = (k_cache.shape[1], k_cache.shape[2])
    rep = Hq // Hkv
    kc = (lambda x, n, axis: torch.repeat_interleave(x, n, dim=axis))(k_cache, rep, axis=1)
    vc = (lambda x, n, axis: torch.repeat_interleave(x, n, dim=axis))(v_cache, rep, axis=1)
    kt = (lambda x, n, axis: torch.repeat_interleave(x, n, dim=axis))(k_tree, rep, axis=1)
    vt = (lambda x, n, axis: torch.repeat_interleave(x, n, dim=axis))(v_tree, rep, axis=1)
    k = torch.concatenate([kc, kt], axis=2)
    v = torch.concatenate([vc, vt], axis=2)
    scale = D ** (-0.5)
    scores = torch.einsum('bhqd,bhkd->bhqk', q, k) * scale
    ctx_mask = torch.ones((B, 1, T, C), dtype=scores.dtype)
    tm = tree_mask[:, None, :, :].clone()
    full_mask = torch.concatenate([ctx_mask, tm], axis=-1)
    scores = scores + (1.0 - full_mask) * -1000000000.0
    p = _softmax(scores, axis=-1)
    return torch.einsum('bhqk,bhkd->bhqd', p, v)
```

```cpp
#include <cuda_runtime.h>
#include <cuda_bf16.h>
#include <cuda.h>
#include <stdint.h>

namespace {

constexpr int kHeadsPerBatch = 32;
constexpr int kNH = 512;
constexpr int kT = 4;
constexpr int kC = 2048;
constexpr int kD = 128;
constexpr int kTileKeys = 128;
constexpr int kTPH = kC / kTileKeys;
constexpr int kSlots = 6;
constexpr int kSlotBytes = kTileKeys * kD * 2;
constexpr int kConsumerWarps = 8;
constexpr int kConsumerThreads = kConsumerWarps * 32;
constexpr int kThreads = kConsumerThreads + 32;
constexpr int kMaxCtas = 256;

constexpr int kSegBytes = 3200;
constexpr int kScrStride = 132;

constexpr int kOffRing = 0;
constexpr int kOffSeg = kOffRing + kSlots * kSlotBytes;
constexpr int kOffScr = kOffSeg + 2 * kSegBytes;
constexpr int kOffML = kOffScr + kConsumerWarps * kT * kScrStride * 4;
constexpr int kOffBar = kOffML + kConsumerWarps * kT * 2 * 4;
constexpr int kOffFlag = kOffBar + 16 * 8;
constexpr int kSmemBytes = kOffFlag + 16 + 1024;

constexpr float kScale = 0.08838834764831845f;
constexpr float kLog2e = 1.4426950408889634f;

struct Partial {
  float o[kT * kD];
  float m[kT];
  float l[kT];
};

__device__ Partial g_partial[kMaxCtas * 2];
__device__ unsigned g_count[kNH];

__device__ __forceinline__ uint32_t smem_u32(const void* p) { return (uint32_t)__cvta_generic_to_shared(p); }

__device__ __forceinline__ void mbar_init(uint32_t bar, uint32_t count) {
  asm volatile("mbarrier.init.shared::cta.b64 [%0], %1;" ::"r"(bar), "r"(count));
}
__device__ __forceinline__ void mbar_expect_tx(uint32_t bar, uint32_t bytes) {
  asm volatile("mbarrier.arrive.expect_tx.shared::cta.b64 _, [%0], %1;" ::"r"(bar), "r"(bytes) : "memory");
}
__device__ __forceinline__ void mbar_arrive(uint32_t bar) {
  asm volatile("mbarrier.arrive.shared::cta.b64 _, [%0];" ::"r"(bar) : "memory");
}
__device__ __forceinline__ bool mbar_try(uint32_t bar, uint32_t parity) {
  uint32_t ok;
  asm volatile("{\n.reg .pred P;\nmbarrier.try_wait.parity.shared::cta.b64 P, [%1], %2;\nselp.u32 %0, 1, 0, P;\n}"
               : "=r"(ok) : "r"(bar), "r"(parity) : "memory");
  return ok != 0;
}
__device__ __forceinline__ void mbar_wait(uint32_t bar, uint32_t parity) {
  if (mbar_try(bar, parity)) return;
  for (uint32_t spin = 0; !mbar_try(bar, parity); ++spin)
    if (spin > (1u << 24)) __trap();
}
__device__ __forceinline__ void bulk_load(uint32_t dst, const void* src, uint32_t bytes, uint32_t bar) {
  asm volatile("cp.async.bulk.shared::cluster.global.mbarrier::complete_tx::bytes [%0], [%1], %2, [%3];"
               ::"r"(dst), "l"(src), "r"(bytes), "r"(bar) : "memory");
}
__device__ __forceinline__ void tma_tile(uint32_t dst, const CUtensorMap* map, int row8, uint32_t bar) {
  asm volatile("cp.async.bulk.tensor.4d.shared::cluster.global.mbarrier::complete_tx::bytes [%0], [%1, {%3,%3,%3,%4}], [%2];"
               ::"r"(dst), "l"(map), "r"(bar), "r"(0), "r"(row8) : "memory");
}
__device__ __forceinline__ void ldsm4(uint32_t (&r)[4], uint32_t addr) {
  asm volatile("ldmatrix.sync.aligned.m8n8.x4.shared.b16 {%0,%1,%2,%3}, [%4];"
               : "=r"(r[0]), "=r"(r[1]), "=r"(r[2]), "=r"(r[3]) : "r"(addr) : "memory");
}
__device__ __forceinline__ void ldsm4t(uint32_t (&r)[4], uint32_t addr) {
  asm volatile("ldmatrix.sync.aligned.m8n8.x4.trans.shared.b16 {%0,%1,%2,%3}, [%4];"
               : "=r"(r[0]), "=r"(r[1]), "=r"(r[2]), "=r"(r[3]) : "r"(addr) : "memory");
}
__device__ __forceinline__ void mma16816(float (&c)[4], const uint32_t (&a)[4], uint32_t b0, uint32_t b1) {
  asm volatile("mma.sync.aligned.m16n8k16.row.col.f32.bf16.bf16.f32 {%0,%1,%2,%3}, {%4,%5,%6,%7}, {%8,%9}, {%0,%1,%2,%3};"
               : "+f"(c[0]), "+f"(c[1]), "+f"(c[2]), "+f"(c[3])
               : "r"(a[0]), "r"(a[1]), "r"(a[2]), "r"(a[3]), "r"(b0), "r"(b1));
}
__device__ __forceinline__ uint32_t movmatrix_t(uint32_t x) {
  uint32_t y;
  asm volatile("movmatrix.sync.aligned.m8n8.trans.b16 %0, %1;" : "=r"(y) : "r"(x));
  return y;
}
__device__ __forceinline__ float ex2(float x) {
  float y;
  asm("ex2.approx.ftz.f32 %0, %1;" : "=f"(y) : "f"(x));
  return y;
}
__device__ __forceinline__ uint32_t pack_bf16(float lo, float hi) {
  uint32_t y;
  asm("cvt.rn.bf16x2.f32 %0, %1, %2;" : "=r"(y) : "f"(hi), "f"(lo));
  return y;
}
__device__ __forceinline__ void consumer_bar() { asm volatile("bar.sync 1, 256;" ::: "memory"); }

struct WarpState {
  float o[8][4];
  float m0, m1, l0, l1;
};

__device__ __forceinline__ void softmax_step(WarpState& st, const float (&x)[4], uint32_t& pb0, uint32_t& pb1) {
  float mx0 = fmaxf(x[0], x[2]), mx1 = fmaxf(x[1], x[3]);
#pragma unroll
  for (int off = 4; off < 32; off <<= 1) {
    mx0 = fmaxf(mx0, __shfl_xor_sync(0xffffffffu, mx0, off));
    mx1 = fmaxf(mx1, __shfl_xor_sync(0xffffffffu, mx1, off));
  }
  const float mn0 = fmaxf(st.m0, mx0), mn1 = fmaxf(st.m1, mx1);
  const float a0 = ex2(st.m0 - mn0), a1 = ex2(st.m1 - mn1);
  const float p0 = ex2(x[0] - mn0), p1 = ex2(x[1] - mn1), p2 = ex2(x[2] - mn0), p3 = ex2(x[3] - mn1);
  st.m0 = mn0; st.m1 = mn1;
  st.l0 = st.l0 * a0 + (p0 + p2);
  st.l1 = st.l1 * a1 + (p1 + p3);
#pragma unroll
  for (int i = 0; i < 8; ++i) {
    st.o[i][0] *= a0; st.o[i][1] *= a1; st.o[i][2] *= a0; st.o[i][3] *= a1;
  }
  pb0 = movmatrix_t(pack_bf16(p0, p1));
  pb1 = movmatrix_t(pack_bf16(p2, p3));
}

struct Segment { int head, t0, t1; bool partial; };

struct Schedule {
  int c, grid, full, nrem, lo, hi, remT;
  __device__ Schedule(int c_, int grid_) : c(c_), grid(grid_) {
    full = kNH / grid;
    remT = (kNH - full * grid) * kTPH;
    lo = remT * c / grid;
    hi = remT * (c + 1) / grid;
    nrem = (hi > lo) ? ((hi - 1) / kTPH - lo / kTPH + 1) : 0;
  }
  __device__ int count() const { return nrem + full; }
  __device__ Segment get(int s) const {
    Segment g;
    if (s < nrem) {
      const int r = lo / kTPH + s;
      g.head = full * grid + r;
      g.t0 = max(lo - r * kTPH, 0);
      g.t1 = min(hi - r * kTPH, kTPH);
      g.partial = true;
    } else {
      g.head = c + (s - nrem) * grid;
      g.t0 = 0; g.t1 = kTPH; g.partial = false;
    }
    return g;
  }
};

__global__ void __launch_bounds__(kThreads, 1)
tree_attn_kernel(const __grid_constant__ CUtensorMap map_k, const __grid_constant__ CUtensorMap map_v,
                 const __nv_bfloat16* __restrict__ q, const __nv_bfloat16* __restrict__ k_tree,
                 const __nv_bfloat16* __restrict__ v_tree, const __nv_bfloat16* __restrict__ mask,
                 __nv_bfloat16* __restrict__ out) {
  extern __shared__ uint8_t smem_raw[];
  const uint32_t raw = smem_u32(smem_raw);
  const uint32_t sb = (raw + 1023u) & ~1023u;
  uint8_t* sp = smem_raw + (sb - raw);

  const uint32_t bar_full = sb + kOffBar;
  const uint32_t bar_empty = bar_full + kSlots * 8;
  const uint32_t bar_segfull = bar_empty + kSlots * 8;
  const uint32_t bar_segempty = bar_segfull + 16;

  const int warp = threadIdx.x >> 5, lane = threadIdx.x & 31;

  if (threadIdx.x == kConsumerThreads) {
    asm volatile("prefetch.tensormap [%0];" ::"l"(&map_k) : "memory");
    asm volatile("prefetch.tensormap [%0];" ::"l"(&map_v) : "memory");
    for (int s = 0; s < kSlots; ++s) {
      mbar_init(bar_full + s * 8, 1);
      mbar_init(bar_empty + s * 8, kConsumerWarps);
    }
    for (int s = 0; s < 2; ++s) {
      mbar_init(bar_segfull + s * 8, 1);
      mbar_init(bar_segempty + s * 8, kConsumerWarps);
    }
    asm volatile("fence.mbarrier_init.release.cluster;" ::: "memory");
  }
  __syncthreads();

  const Schedule sched(blockIdx.x, gridDim.x);
  const int nseg = sched.count();

  if (warp == kConsumerWarps) {
    if (lane == 0) {
      int slot = 0; uint32_t phase = 1;
      for (int s = 0; s < nseg; ++s) {
        const Segment sg = sched.get(s);
        const int buf = s & 1;
        const uint32_t sbuf = sb + kOffSeg + buf * kSegBytes;
        mbar_wait(bar_segempty + buf * 8, ((s >> 1) & 1) ^ 1);
        const bool tree = sg.t1 == kTPH;
        mbar_expect_tx(bar_segfull + buf * 8, tree ? 3 * 1024 + 32 : 1024);
        bulk_load(sbuf, q + (size_t)sg.head * (kT * kD), 1024, bar_segfull + buf * 8);
        if (tree) {
          bulk_load(sbuf + 1024, k_tree + (size_t)sg.head * (kT * kD), 1024, bar_segfull + buf * 8);
          bulk_load(sbuf + 2048, v_tree + (size_t)sg.head * (kT * kD), 1024, bar_segfull + buf * 8);
          bulk_load(sbuf + 3072, mask + (size_t)(sg.head / kHeadsPerBatch) * (kT * kT), 32, bar_segfull + buf * 8);
        }
        for (int t = sg.t0; t < sg.t1; ++t) {
          const int row8 = (sg.head * kC + t * kTileKeys) >> 3;
#pragma unroll
          for (int kv = 0; kv < 2; ++kv) {
            mbar_wait(bar_empty + slot * 8, phase);
            mbar_expect_tx(bar_full + slot * 8, kSlotBytes);
            tma_tile(sb + kOffRing + slot * kSlotBytes, kv ? &map_v : &map_k, row8, bar_full + slot * 8);
            if (++slot == kSlots) { slot = 0; phase ^= 1; }
          }
        }
      }
    }
    return;
  }

  const int g = lane >> 2, t4 = lane & 3;
  const int mi = lane >> 3, r = lane & 7;
  const uint32_t koff = (2 * warp + (mi & 1)) * 2048 + r * 128;
  const uint32_t kxor = ((mi >> 1) ^ r) << 4;
  const uint32_t voff = (2 * warp + (mi >> 1)) * 2048 + r * 128;
  const uint32_t vxor = ((mi & 1) ^ r) << 4;

  float* scr = reinterpret_cast<float*>(sp + kOffScr);
  float* scr_m = reinterpret_cast<float*>(sp + kOffML);
  float* scr_l = scr_m + kConsumerWarps * kT;
  volatile uint32_t* flag = reinterpret_cast<volatile uint32_t*>(sp + kOffFlag);

  int slot = 0; uint32_t phase = 0;
  for (int s = 0; s < nseg; ++s) {
    const Segment sg = sched.get(s);
    const int buf = s & 1;
    const uint32_t sbuf = sb + kOffSeg + buf * kSegBytes;
    mbar_wait(bar_segfull + buf * 8, (s >> 1) & 1);

    uint32_t qf[8][2];
    {
      const uint32_t* qs = reinterpret_cast<const uint32_t*>(sp + kOffSeg + buf * kSegBytes);
#pragma unroll
      for (int kk = 0; kk < 8; ++kk) {
        qf[kk][0] = (g < kT) ? qs[(g & 3) * 64 + kk * 8 + t4] : 0u;
        qf[kk][1] = (g < kT) ? qs[(g & 3) * 64 + kk * 8 + 4 + t4] : 0u;
      }
    }

    WarpState st;
#pragma unroll
    for (int i = 0; i < 8; ++i) { st.o[i][0] = st.o[i][1] = st.o[i][2] = st.o[i][3] = 0.f; }
    st.m0 = st.m1 = -INFINITY;
    st.l0 = st.l1 = 0.f;

    if (sg.t1 == kTPH && warp == 0) {
      float c[4] = {0.f, 0.f, 0.f, 0.f};
      const uint32_t ka = sbuf + 1024 + (r & 3) * 256 + (mi >> 1) * 16;
#pragma unroll
      for (int kk = 0; kk < 8; ++kk) {
        uint32_t a[4];
        ldsm4(a, ka + kk * 32);
        mma16816(c, a, qf[kk][0], qf[kk][1]);
      }
      const __nv_bfloat16* ms = reinterpret_cast<const __nv_bfloat16*>(sp + kOffSeg + buf * kSegBytes + 3072);
      const int q0 = (2 * t4) & 3;
      const float mk0 = __bfloat162float(ms[q0 * kT + (g & 3)]);
      const float mk1 = __bfloat162float(ms[(q0 + 1) * kT + (g & 3)]);
      float x[4];
      x[0] = (g < kT) ? fmaf(c[0], kScale, (1.0f - mk0) * -1000000000.0f) * kLog2e : -INFINITY;
      x[1] = (g < kT) ? fmaf(c[1], kScale, (1.0f - mk1) * -1000000000.0f) * kLog2e : -INFINITY;
      x[2] = -INFINITY;
      x[3] = -INFINITY;
      uint32_t pb0, pb1;
      softmax_step(st, x, pb0, pb1);
      const uint32_t va = sbuf + 2048 + (r & 3) * 256 + (mi & 1) * 16;
#pragma unroll
      for (int i = 0; i < 8; ++i) {
        uint32_t a[4];
        ldsm4t(a, va + i * 32);
        mma16816(st.o[i], a, pb0, pb1);
      }
    }
    __syncwarp();
    if (lane == 0) mbar_arrive(bar_segempty + buf * 8);

    for (int t = sg.t0; t < sg.t1; ++t) {
      uint32_t pb0, pb1;
      {
        mbar_wait(bar_full + slot * 8, phase);
        const uint32_t base = sb + kOffRing + slot * kSlotBytes + koff;
        float ca[4] = {0.f, 0.f, 0.f, 0.f}, cb[4] = {0.f, 0.f, 0.f, 0.f};
        uint32_t a[8][4];
#pragma unroll
        for (int kk = 0; kk < 8; ++kk) ldsm4(a[kk], base + (kk >> 2) * 1024 + (kxor ^ ((kk & 3) << 5)));
#pragma unroll
        for (int kk = 0; kk < 8; kk += 2) {
          mma16816(ca, a[kk], qf[kk][0], qf[kk][1]);
          mma16816(cb, a[kk + 1], qf[kk + 1][0], qf[kk + 1][1]);
        }
        __syncwarp();
        if (lane == 0) mbar_arrive(bar_empty + slot * 8);
        if (++slot == kSlots) { slot = 0; phase ^= 1; }
        const float sc = kScale * kLog2e;
        float x[4];
#pragma unroll
        for (int i = 0; i < 4; ++i) x[i] = (ca[i] + cb[i]) * sc;
        softmax_step(st, x, pb0, pb1);
      }
      {
        mbar_wait(bar_full + slot * 8, phase);
        const uint32_t base = sb + kOffRing + slot * kSlotBytes + voff;
        uint32_t a[8][4];
#pragma unroll
        for (int i = 0; i < 8; ++i) ldsm4t(a[i], base + (i >> 2) * 1024 + (vxor ^ ((i & 3) << 5)));
#pragma unroll
        for (int i = 0; i < 8; ++i) mma16816(st.o[i], a[i], pb0, pb1);
        __syncwarp();
        if (lane == 0) mbar_arrive(bar_empty + slot * 8);
        if (++slot == kSlots) { slot = 0; phase ^= 1; }
      }
    }

#pragma unroll
    for (int off = 4; off < 32; off <<= 1) {
      st.l0 += __shfl_xor_sync(0xffffffffu, st.l0, off);
      st.l1 += __shfl_xor_sync(0xffffffffu, st.l1, off);
    }
    if (t4 < 2) {
      float* row0 = scr + (warp * kT + 2 * t4) * kScrStride + g;
      float* row1 = row0 + kScrStride;
#pragma unroll
      for (int i = 0; i < 8; ++i) {
        row0[16 * i] = st.o[i][0];
        row1[16 * i] = st.o[i][1];
        row0[16 * i + 8] = st.o[i][2];
        row1[16 * i + 8] = st.o[i][3];
      }
      if (g == 0) {
        scr_m[warp * kT + 2 * t4] = st.m0; scr_m[warp * kT + 2 * t4 + 1] = st.m1;
        scr_l[warp * kT + 2 * t4] = st.l0; scr_l[warp * kT + 2 * t4 + 1] = st.l1;
      }
    }
    consumer_bar();
    const int qi = threadIdx.x >> 6, d = (threadIdx.x & 63) * 2;
    float M = -INFINITY;
#pragma unroll
    for (int w = 0; w < kConsumerWarps; ++w) M = fmaxf(M, scr_m[w * kT + qi]);
    float L = 0.f, ox = 0.f, oy = 0.f;
#pragma unroll
    for (int w = 0; w < kConsumerWarps; ++w) {
      const float a = ex2(scr_m[w * kT + qi] - M);
      const float2 v = *reinterpret_cast<const float2*>(scr + (w * kT + qi) * kScrStride + d);
      L += a * scr_l[w * kT + qi];
      ox += a * v.x;
      oy += a * v.y;
    }
    __nv_bfloat16* optr = out + ((size_t)sg.head * kT + qi) * kD + d;
    if (!sg.partial) {
      const float inv = 1.0f / L;
      *reinterpret_cast<uint32_t*>(optr) = pack_bf16(ox * inv, oy * inv);
      if (s + 1 < nseg) consumer_bar();
    } else {
      Partial* p = &g_partial[blockIdx.x * 2 + s];
      __stcg(reinterpret_cast<float2*>(&p->o[qi * kD + d]), make_float2(ox, oy));
      if (d == 0) { __stcg(&p->m[qi], M); __stcg(&p->l[qi], L); }
      __threadfence();
      consumer_bar();
      if (threadIdx.x == 0) {
        const unsigned n = sg.t1 - sg.t0;
        const unsigned old = atomicAdd(&g_count[sg.head], n);
        const bool last = old + n == kTPH;
        if (last) g_count[sg.head] = 0;
        *flag = last;
      }
      consumer_bar();
      if (*flag) {
        __threadfence();
        const int x0 = (sg.head - sched.full * sched.grid) * kTPH;
        const int c_lo = ((x0 + 1) * sched.grid - 1) / sched.remT;
        const int c_hi = ((x0 + kTPH) * sched.grid - 1) / sched.remT;
        float Mg = -INFINITY, Lg = 0.f, gx = 0.f, gy = 0.f;
        for (int c = c_lo; c <= c_hi; ++c) {
          const int lo = sched.remT * c / sched.grid, hi = sched.remT * (c + 1) / sched.grid;
          if (hi <= lo) continue;
          const Partial* pp = &g_partial[c * 2 + (lo < x0 ? 1 : 0)];
          const float pm = __ldcg(&pp->m[qi]), pl = __ldcg(&pp->l[qi]);
          const float2 v = __ldcg(reinterpret_cast<const float2*>(&pp->o[qi * kD + d]));
          const float mn = fmaxf(Mg, pm);
          const float a = ex2(Mg - mn), b = ex2(pm - mn);
          Lg = Lg * a + pl * b;
          gx = gx * a + v.x * b;
          gy = gy * a + v.y * b;
          Mg = mn;
        }
        const float inv = 1.0f / Lg;
        *reinterpret_cast<uint32_t*>(optr) = pack_bf16(gx * inv, gy * inv);
      }
      consumer_bar();
    }
  }
}

typedef CUresult (*EncodeTiledFn)(CUtensorMap*, CUtensorMapDataType, cuuint32_t, void*, const cuuint64_t*,
                                  const cuuint64_t*, const cuuint32_t*, const cuuint32_t*, CUtensorMapInterleave,
                                  CUtensorMapSwizzle, CUtensorMapL2promotion, CUtensorMapFloatOOBfill);

bool make_map(EncodeTiledFn enc, CUtensorMap* m, void* base) {
  const cuuint64_t rows = (cuuint64_t)kNH * kC;
  cuuint64_t dims[4] = {64, 8, 2, rows / 8};
  cuuint64_t strides[3] = {256, 128, 2048};
  cuuint32_t box[4] = {64, 8, 2, kTileKeys / 8};
  cuuint32_t es[4] = {1, 1, 1, 1};
  return enc(m, CU_TENSOR_MAP_DATA_TYPE_BFLOAT16, 4, base, dims, strides, box, es, CU_TENSOR_MAP_INTERLEAVE_NONE,
             CU_TENSOR_MAP_SWIZZLE_128B, CU_TENSOR_MAP_L2_PROMOTION_NONE,
             CU_TENSOR_MAP_FLOAT_OOB_FILL_NONE) == CUDA_SUCCESS;
}

}

extern "C" void kernel_launch(void* const* d_in, const int* in_sizes, int n_in, void* d_out, int out_size) {
  (void)in_sizes; (void)n_in; (void)out_size;
  static EncodeTiledFn enc = nullptr;
  static int grid = 0;
  if (!enc) {
    void* fn = nullptr;
    cudaDriverEntryPointQueryResult qr;
    cudaGetDriverEntryPoint("cuTensorMapEncodeTiled", &fn, cudaEnableDefault, &qr);
    enc = (EncodeTiledFn)fn;
    int dev = 0, sms = 0;
    cudaGetDevice(&dev);
    cudaDeviceGetAttribute(&sms, cudaDevAttrMultiProcessorCount, dev);
    grid = sms < kMaxCtas ? sms : kMaxCtas;
    cudaFuncSetAttribute(tree_attn_kernel, cudaFuncAttributeMaxDynamicSharedMemorySize, kSmemBytes);
  }
  CUtensorMap map_k, map_v;
  if (!enc || !make_map(enc, &map_k, d_in[1]) || !make_map(enc, &map_v, d_in[2])) return;
  tree_attn_kernel<<<grid, kThreads, kSmemBytes, cudaStreamPerThread>>>(
      map_k, map_v, (const __nv_bfloat16*)d_in[0], (const __nv_bfloat16*)d_in[3], (const __nv_bfloat16*)d_in[4],
      (const __nv_bfloat16*)d_in[5], (__nv_bfloat16*)d_out);
}
```

```cpp
#include <cuda_runtime.h>
#include <cuda_bf16.h>
#include <cuda.h>
#include <stdint.h>

namespace {

constexpr int kHeadsPerBatch = 32;
constexpr int kNH = 512;
constexpr int kT = 4;
constexpr int kC = 2048;
constexpr int kD = 128;
constexpr int kTileKeys = 128;
constexpr int kTPH = kC / kTileKeys;
constexpr int kTotalTiles = kNH * kTPH;
#define KSLOTS 6
#define LEAD 0.5f
#define PSTART 3
constexpr int kSlots = KSLOTS;
constexpr int kSlotBytes = kTileKeys * kD * 2;
constexpr int kConsumerWarps = 8;
constexpr int kConsumerThreads = kConsumerWarps * 32;
constexpr int kProducerWarp = kConsumerWarps;
constexpr int kFinalizerWarp = kConsumerWarps + 1;
constexpr int kPacerWarp = kConsumerWarps + 2;
constexpr int kThreads = kConsumerThreads + 96;
constexpr int kMaxCtas = 256;

constexpr int kSegBytes = 3200;

constexpr int kOffRing = 0;
constexpr int kOffSeg = kOffRing + kSlots * kSlotBytes;
constexpr int kOffScr = kOffSeg + 2 * kSegBytes;
constexpr int kOffPf = kOffScr + kConsumerWarps * kD * kT * 4;
constexpr int kOffML = kOffPf + kConsumerWarps * 32 * 8;
constexpr int kPartBytes = (kT * kD + 2 * kT) * 4;
constexpr int kOffPart = kOffML + kConsumerWarps * 2 * 16;
constexpr int kOffBar = kOffPart + 2 * kPartBytes;
constexpr int kOffPace = kOffBar + (2 * kSlots + 6) * 8;
constexpr int kSmemBytes = kOffPace + 8 + 1024;

constexpr float kScale = 0.08838834764831845f;
constexpr float kLog2e = 1.4426950408889634f;

struct __align__(16) Partial {
  float o[kT * kD];
  float m[kT];
  float l[kT];
};

__device__ Partial g_partial[kMaxCtas * 2];
__device__ unsigned g_count[kNH];
__device__ unsigned g_progress;

__device__ __forceinline__ uint32_t smem_u32(const void* p) { return (uint32_t)__cvta_generic_to_shared(p); }

__device__ __forceinline__ void mbar_init(uint32_t bar, uint32_t count) {
  asm volatile("mbarrier.init.shared::cta.b64 [%0], %1;" ::"r"(bar), "r"(count));
}
__device__ __forceinline__ void mbar_expect_tx(uint32_t bar, uint32_t bytes) {
  asm volatile("mbarrier.arrive.expect_tx.shared::cta.b64 _, [%0], %1;" ::"r"(bar), "r"(bytes) : "memory");
}
__device__ __forceinline__ void mbar_arrive(uint32_t bar) {
  asm volatile("mbarrier.arrive.shared::cta.b64 _, [%0];" ::"r"(bar) : "memory");
}
__device__ __forceinline__ bool mbar_try(uint32_t bar, uint32_t parity) {
  uint32_t ok;
  asm volatile("{\n.reg .pred P;\nmbarrier.try_wait.parity.shared::cta.b64 P, [%1], %2;\nselp.u32 %0, 1, 0, P;\n}"
               : "=r"(ok) : "r"(bar), "r"(parity) : "memory");
  return ok != 0;
}
__device__ __forceinline__ void mbar_wait(uint32_t bar, uint32_t parity) {
  if (mbar_try(bar, parity)) return;
  for (uint32_t spin = 0; !mbar_try(bar, parity); ++spin)
    if (spin > (1u << 24)) __trap();
}
__device__ __forceinline__ void bulk_load(uint32_t dst, const void* src, uint32_t bytes, uint32_t bar) {
  asm volatile("cp.async.bulk.shared::cluster.global.mbarrier::complete_tx::bytes [%0], [%1], %2, [%3];"
               ::"r"(dst), "l"(src), "r"(bytes), "r"(bar) : "memory");
}
__device__ __forceinline__ void tma_tile(uint32_t dst, const CUtensorMap* map, int row8, uint32_t bar, uint64_t policy) {
  asm volatile("cp.async.bulk.tensor.4d.shared::cluster.global.mbarrier::complete_tx::bytes.L2::cache_hint"
               " [%0], [%1, {%3,%3,%3,%4}], [%2], %5;"
               ::"r"(dst), "l"(map), "r"(bar), "r"(0), "r"(row8), "l"(policy) : "memory");
}
__device__ __forceinline__ void ldsm4(uint32_t (&r)[4], uint32_t addr) {
  asm volatile("ldmatrix.sync.aligned.m8n8.x4.shared.b16 {%0,%1,%2,%3}, [%4];"
               : "=r"(r[0]), "=r"(r[1]), "=r"(r[2]), "=r"(r[3]) : "r"(addr) : "memory");
}
__device__ __forceinline__ void ldsm4t(uint32_t (&r)[4], uint32_t addr) {
  asm volatile("ldmatrix.sync.aligned.m8n8.x4.trans.shared.b16 {%0,%1,%2,%3}, [%4];"
               : "=r"(r[0]), "=r"(r[1]), "=r"(r[2]), "=r"(r[3]) : "r"(addr) : "memory");
}
__device__ __forceinline__ void mma16816(float (&c)[4], const uint32_t (&a)[4], uint32_t b0, uint32_t b1) {
  asm volatile("mma.sync.aligned.m16n8k16.row.col.f32.bf16.bf16.f32 {%0,%1,%2,%3}, {%4,%5,%6,%7}, {%8,%9}, {%0,%1,%2,%3};"
               : "+f"(c[0]), "+f"(c[1]), "+f"(c[2]), "+f"(c[3])
               : "r"(a[0]), "r"(a[1]), "r"(a[2]), "r"(a[3]), "r"(b0), "r"(b1));
}
__device__ __forceinline__ uint32_t movmatrix_t(uint32_t x) {
  uint32_t y;
  asm volatile("movmatrix.sync.aligned.m8n8.trans.b16 %0, %1;" : "=r"(y) : "r"(x));
  return y;
}
__device__ __forceinline__ float ex2(float x) {
  float y;
  asm("ex2.approx.ftz.f32 %0, %1;" : "=f"(y) : "f"(x));
  return y;
}
__device__ __forceinline__ float rcp(float x) {
  float y;
  asm("rcp.approx.ftz.f32 %0, %1;" : "=f"(y) : "f"(x));
  return y;
}
__device__ __forceinline__ uint32_t pack_bf16(float lo, float hi) {
  uint32_t y;
  asm("cvt.rn.bf16x2.f32 %0, %1, %2;" : "=r"(y) : "f"(hi), "f"(lo));
  return y;
}
__device__ __forceinline__ void consumer_bar() { asm volatile("bar.sync 1, 256;" ::: "memory"); }

struct WarpState {
  float o[8][4];
  float m0, m1, l0, l1;
};

__device__ __forceinline__ void softmax_update(WarpState& st, const float (&x)[4], float (&p)[4], float& a0, float& a1) {
  float mx0 = fmaxf(x[0], x[2]), mx1 = fmaxf(x[1], x[3]);
#pragma unroll
  for (int off = 4; off < 32; off <<= 1) {
    mx0 = fmaxf(mx0, __shfl_xor_sync(0xffffffffu, mx0, off));
    mx1 = fmaxf(mx1, __shfl_xor_sync(0xffffffffu, mx1, off));
  }
  const float mn0 = fmaxf(st.m0, mx0), mn1 = fmaxf(st.m1, mx1);
  a0 = ex2(st.m0 - mn0); a1 = ex2(st.m1 - mn1);
  p[0] = ex2(x[0] - mn0); p[1] = ex2(x[1] - mn1); p[2] = ex2(x[2] - mn0); p[3] = ex2(x[3] - mn1);
  st.m0 = mn0; st.m1 = mn1;
  st.l0 = st.l0 * a0 + (p[0] + p[2]);
  st.l1 = st.l1 * a1 + (p[1] + p[3]);
}
__device__ __forceinline__ void softmax_step(WarpState& st, const float (&x)[4], uint32_t& pb0, uint32_t& pb1) {
  float p[4], a0, a1;
  softmax_update(st, x, p, a0, a1);
#pragma unroll
  for (int i = 0; i < 8; ++i) {
    st.o[i][0] *= a0; st.o[i][1] *= a1; st.o[i][2] *= a0; st.o[i][3] *= a1;
  }
  pb0 = movmatrix_t(pack_bf16(p[0], p[1]));
  pb1 = movmatrix_t(pack_bf16(p[2], p[3]));
}

struct Segment { int head, t0, t1; bool partial; };

struct Schedule {
  int c, grid, full, nrem, lo, hi, remT;
  __device__ Schedule(int c_, int grid_) : c(c_), grid(grid_) {
    full = kNH / grid;
    remT = (kNH - full * grid) * kTPH;
    lo = remT * c / grid;
    hi = remT * (c + 1) / grid;
    nrem = (hi > lo) ? ((hi - 1) / kTPH - lo / kTPH + 1) : 0;
  }
  __device__ int count() const { return nrem + full; }
  __device__ Segment get(int s) const {
    Segment g;
    if (s < nrem) {
      const int r = lo / kTPH + s;
      g.head = full * grid + r;
      g.t0 = max(lo - r * kTPH, 0);
      g.t1 = min(hi - r * kTPH, kTPH);
      g.partial = true;
    } else {
      g.head = c + (s - nrem) * grid;
      g.t0 = 0; g.t1 = kTPH; g.partial = false;
    }
    return g;
  }
};

template <int kGrid>
__global__ void __launch_bounds__(kThreads, 1)
tree_attn_kernel(const __grid_constant__ CUtensorMap map_k, const __grid_constant__ CUtensorMap map_v,
                 const __nv_bfloat16* __restrict__ q, const __nv_bfloat16* __restrict__ k_tree,
                 const __nv_bfloat16* __restrict__ v_tree, const __nv_bfloat16* __restrict__ mask,
                 __nv_bfloat16* __restrict__ out) {
  extern __shared__ uint8_t smem_raw[];
  const uint32_t raw = smem_u32(smem_raw);
  const uint32_t sb = (raw + 1023u) & ~1023u;
  uint8_t* sp = smem_raw + (sb - raw);

  const uint32_t bar_full = sb + kOffBar;
  const uint32_t bar_empty = bar_full + kSlots * 8;
  const uint32_t bar_segfull = bar_empty + kSlots * 8;
  const uint32_t bar_segempty = bar_segfull + 16;
  const uint32_t bar_part = bar_segempty + 16;
  volatile uint32_t* s_pace = reinterpret_cast<volatile uint32_t*>(sp + kOffPace);

  const int warp = threadIdx.x >> 5, lane = threadIdx.x & 31;
  const Schedule sched(blockIdx.x, kGrid ? kGrid : (int)gridDim.x);
  const int nseg = sched.count();

  if (warp == kProducerWarp) {
    if (lane == 0) {
      asm volatile("prefetch.tensormap [%0];" ::"l"(&map_k) : "memory");
      asm volatile("prefetch.tensormap [%0];" ::"l"(&map_v) : "memory");
      for (int s = 0; s < kSlots; ++s) {
        mbar_init(bar_full + s * 8, 1);
        mbar_init(bar_empty + s * 8, kConsumerWarps);
      }
      for (int s = 0; s < 2; ++s) {
        mbar_init(bar_segfull + s * 8, 1);
        mbar_init(bar_segempty + s * 8, kConsumerWarps);
        mbar_init(bar_part + s * 8, kConsumerWarps);
      }
      s_pace[0] = 0;
      s_pace[1] = 0;
      asm volatile("fence.mbarrier_init.release.cluster;" ::: "memory");
      asm volatile("fence.proxy.async.shared::cta;" ::: "memory");
    }
    __syncwarp();
    asm volatile("bar.arrive 2, %0;" ::"n"(kThreads) : "memory");
    if (lane == 0) {
      uint64_t policy;
      asm volatile("createpolicy.fractional.L2::evict_first.b64 %0, 1.0;" : "=l"(policy));
      int slot = 0; uint32_t phase = 1;
      const int ntiles = (sched.hi - sched.lo) + sched.full * kTPH;
      const float per = (float)kTotalTiles / (float)ntiles;
      int ti = 0; bool pace = true;
      for (int s = 0; s < nseg; ++s) {
        const Segment sg = sched.get(s);
        for (int t = sg.t0; t < sg.t1; ++t) {
          const int row8 = (sg.head * kC + t * kTileKeys) >> 3;
#pragma unroll
          for (int kv = 0; kv < 2; ++kv) {
            mbar_wait(bar_empty + slot * 8, phase);
            if (kv == 0 && pace && ti >= PSTART) {
              const int need = (int)(((float)ti - LEAD) * per);
              for (int spin = 0; (int)s_pace[0] < need; ++spin)
                if (spin > 200000) { pace = false; break; }
            }
            mbar_expect_tx(bar_full + slot * 8, kSlotBytes);
            tma_tile(sb + kOffRing + slot * kSlotBytes, kv ? &map_v : &map_k, row8, bar_full + slot * 8, policy);
            if (++slot == kSlots) { slot = 0; phase ^= 1; }
            if (kv == 0) {
              asm volatile("red.relaxed.gpu.global.add.u32 [%0], 1;" ::"l"(&g_progress) : "memory");
              if (++ti == ntiles) s_pace[1] = 1;
              if (t == sg.t0) {
                const int buf = s & 1;
                const uint32_t sbuf = sb + kOffSeg + buf * kSegBytes;
                const uint32_t bar = bar_segfull + buf * 8;
                const bool tree = sg.t1 == kTPH;
                mbar_wait(bar_segempty + buf * 8, ((s >> 1) & 1) ^ 1);
                mbar_expect_tx(bar, tree ? 3 * 1024 + 32 : 1024);
                bulk_load(sbuf, q + (size_t)sg.head * (kT * kD), 1024, bar);
                if (tree) {
                  bulk_load(sbuf + 1024, k_tree + (size_t)sg.head * (kT * kD), 1024, bar);
                  bulk_load(sbuf + 2048, v_tree + (size_t)sg.head * (kT * kD), 1024, bar);
                  bulk_load(sbuf + 3072, mask + (size_t)(sg.head / kHeadsPerBatch) * (kT * kT), 32, bar);
                }
              }
            }
          }
        }
      }
    }
    return;
  }
  asm volatile("bar.sync 2, %0;" ::"n"(kThreads) : "memory");

  if (warp == kPacerWarp) {
    if (lane == 0) {
      unsigned base = 0;
      for (int spin = 0; spin < (1 << 22); ++spin) {
        unsigned v;
        asm volatile("ld.relaxed.gpu.global.u32 %0, [%1];" : "=r"(v) : "l"(&g_progress) : "memory");
        if (spin == 0) base = v & ~(unsigned)(kTotalTiles - 1);
        s_pace[0] = v - base;
        if (s_pace[1]) break;
      }
    }
    return;
  }

  if (warp == kFinalizerWarp) {
    for (int s = 0; s < sched.nrem; ++s) {
      const Segment sg = sched.get(s);
      mbar_wait(bar_part + s * 8, 0);
      const float4* src = reinterpret_cast<const float4*>(sp + kOffPart + s * kPartBytes);
      float4* dst = reinterpret_cast<float4*>(&g_partial[blockIdx.x * 2 + s]);
#pragma unroll
      for (int i = 0; i < kT; ++i) __stcg(dst + lane + 32 * i, src[lane + 32 * i]);
      if (lane < 2) __stcg(dst + 128 + lane, src[128 + lane]);
      __threadfence();
      __syncwarp();
      unsigned last = 0;
      if (lane == 0) {
        const unsigned n = sg.t1 - sg.t0;
        last = atomicAdd(&g_count[sg.head], n) + n == kTPH;
        if (last) g_count[sg.head] = 0;
      }
      last = __shfl_sync(0xffffffffu, last, 0);
      if (last) {
        __threadfence();
        const int x0 = (sg.head - sched.full * sched.grid) * kTPH;
        const int c_lo = ((x0 + 1) * sched.grid - 1) / sched.remT;
        const int c_hi = ((x0 + kTPH) * sched.grid - 1) / sched.remT;
        float M[kT], L[kT];
        float4 O[kT];
#pragma unroll
        for (int i = 0; i < kT; ++i) { M[i] = -INFINITY; L[i] = 0.f; O[i] = make_float4(0.f, 0.f, 0.f, 0.f); }
        for (int c = c_lo; c <= c_hi; ++c) {
          const int lo = sched.remT * c / sched.grid, hi = sched.remT * (c + 1) / sched.grid;
          if (hi <= lo) continue;
          const float4* pp = reinterpret_cast<const float4*>(&g_partial[c * 2 + (lo < x0 ? 1 : 0)]);
          const float4 pm4 = __ldcg(pp + 128), pl4 = __ldcg(pp + 129);
          const float pm[kT] = {pm4.x, pm4.y, pm4.z, pm4.w}, pl[kT] = {pl4.x, pl4.y, pl4.z, pl4.w};
#pragma unroll
          for (int i = 0; i < kT; ++i) {
            const float4 v = __ldcg(pp + lane + 32 * i);
            const float mn = fmaxf(M[i], pm[i]);
            const float a = ex2(M[i] - mn), b = ex2(pm[i] - mn);
            L[i] = L[i] * a + pl[i] * b;
            O[i].x = O[i].x * a + v.x * b; O[i].y = O[i].y * a + v.y * b;
            O[i].z = O[i].z * a + v.z * b; O[i].w = O[i].w * a + v.w * b;
            M[i] = mn;
          }
        }
#pragma unroll
        for (int i = 0; i < kT; ++i) {
          const float inv = 1.0f / L[i];
          *reinterpret_cast<uint2*>(out + ((size_t)sg.head * kT + i) * kD + 4 * lane) =
              make_uint2(pack_bf16(O[i].x * inv, O[i].y * inv), pack_bf16(O[i].z * inv, O[i].w * inv));
        }
      }
    }
    return;
  }

  const int g = lane >> 2, t4 = lane & 3;
  const int mi = lane >> 3, r = lane & 7;
  const uint32_t koff = (2 * warp + (mi & 1)) * 2048 + r * 128;
  const uint32_t kxor = ((mi >> 1) ^ r) << 4;
  const uint32_t voff = (2 * warp + (mi >> 1)) * 2048 + r * 128;
  const uint32_t vxor = ((mi & 1) ^ r) << 4;
  const uint32_t voff_last = (mi >> 1) * 2048 + r * 128 + (warp >> 2) * 1024 + (vxor ^ ((warp & 3) << 5));

  float2* scr = reinterpret_cast<float2*>(sp + kOffScr);
  uint2* pfrag = reinterpret_cast<uint2*>(sp + kOffPf);
  float4* scr_ml = reinterpret_cast<float4*>(sp + kOffML);

  int slot = 0; uint32_t phase = 0;
  for (int s = 0; s < nseg; ++s) {
    const Segment sg = sched.get(s);
    const int buf = s & 1;
    const uint32_t sbuf = sb + kOffSeg + buf * kSegBytes;
    mbar_wait(bar_segfull + buf * 8, (s >> 1) & 1);

    uint32_t qf[8][2];
    {
      const uint32_t* qs = reinterpret_cast<const uint32_t*>(sp + kOffSeg + buf * kSegBytes);
#pragma unroll
      for (int kk = 0; kk < 8; ++kk) {
        qf[kk][0] = (g < kT) ? qs[(g & 3) * 64 + kk * 8 + t4] : 0u;
        qf[kk][1] = (g < kT) ? qs[(g & 3) * 64 + kk * 8 + 4 + t4] : 0u;
      }
    }

    WarpState st;
#pragma unroll
    for (int i = 0; i < 8; ++i) { st.o[i][0] = st.o[i][1] = st.o[i][2] = st.o[i][3] = 0.f; }
    st.m0 = st.m1 = -INFINITY;
    st.l0 = st.l1 = 0.f;

    if (sg.t1 == kTPH && warp == 0) {
      float c[4] = {0.f, 0.f, 0.f, 0.f};
      const uint32_t ka = sbuf + 1024 + (r & 3) * 256 + (mi >> 1) * 16;
#pragma unroll
      for (int kk = 0; kk < 8; ++kk) {
        uint32_t a[4];
        ldsm4(a, ka + kk * 32);
        mma16816(c, a, qf[kk][0], qf[kk][1]);
      }
      const __nv_bfloat16* ms = reinterpret_cast<const __nv_bfloat16*>(sp + kOffSeg + buf * kSegBytes + 3072);
      const int q0 = (2 * t4) & 3;
      const float mk0 = __bfloat162float(ms[q0 * kT + (g & 3)]);
      const float mk1 = __bfloat162float(ms[(q0 + 1) * kT + (g & 3)]);
      float x[4];
      x[0] = (g < kT) ? fmaf(c[0], kScale, (1.0f - mk0) * -1000000000.0f) * kLog2e : -INFINITY;
      x[1] = (g < kT) ? fmaf(c[1], kScale, (1.0f - mk1) * -1000000000.0f) * kLog2e : -INFINITY;
      x[2] = -INFINITY;
      x[3] = -INFINITY;
      uint32_t pb0, pb1;
      softmax_step(st, x, pb0, pb1);
      const uint32_t va = sbuf + 2048 + (r & 3) * 256 + (mi & 1) * 16;
#pragma unroll
      for (int i = 0; i < 8; ++i) {
        uint32_t a[4];
        ldsm4t(a, va + i * 32);
        mma16816(st.o[i], a, pb0, pb1);
      }
    }
    __syncwarp();
    if (lane == 0) mbar_arrive(bar_segempty + buf * 8);

    auto scores = [&](float (&x)[4]) {
      mbar_wait(bar_full + slot * 8, phase);
      const uint32_t base = sb + kOffRing + slot * kSlotBytes + koff;
      float ca[4] = {0.f, 0.f, 0.f, 0.f}, cb[4] = {0.f, 0.f, 0.f, 0.f};
      uint32_t a[8][4];
#pragma unroll
      for (int kk = 0; kk < 8; ++kk) ldsm4(a[kk], base + (kk >> 2) * 1024 + (kxor ^ ((kk & 3) << 5)));
#pragma unroll
      for (int kk = 0; kk < 8; kk += 2) {
        mma16816(ca, a[kk], qf[kk][0], qf[kk][1]);
        mma16816(cb, a[kk + 1], qf[kk + 1][0], qf[kk + 1][1]);
      }
      __syncwarp();
      if (lane == 0) mbar_arrive(bar_empty + slot * 8);
      if (++slot == kSlots) { slot = 0; phase ^= 1; }
      const float sc = kScale * kLog2e;
#pragma unroll
      for (int i = 0; i < 4; ++i) x[i] = (ca[i] + cb[i]) * sc;
    };

    for (int t = sg.t0; t + 1 < sg.t1; ++t) {
      float x[4];
      uint32_t pb0, pb1;
      scores(x);
      softmax_step(st, x, pb0, pb1);
      mbar_wait(bar_full + slot * 8, phase);
      const uint32_t base = sb + kOffRing + slot * kSlotBytes + voff;
      uint32_t a[8][4];
#pragma unroll
      for (int i = 0; i < 8; ++i) ldsm4t(a[i], base + (i >> 2) * 1024 + (vxor ^ ((i & 3) << 5)));
#pragma unroll
      for (int i = 0; i < 8; ++i) mma16816(st.o[i], a[i], pb0, pb1);
      __syncwarp();
      if (lane == 0) mbar_arrive(bar_empty + slot * 8);
      if (++slot == kSlots) { slot = 0; phase ^= 1; }
    }

    float x[4], p[4], a0, a1;
    scores(x);
    softmax_update(st, x, p, a0, a1);
#pragma unroll
    for (int off = 4; off < 32; off <<= 1) {
      st.l0 += __shfl_xor_sync(0xffffffffu, st.l0, off);
      st.l1 += __shfl_xor_sync(0xffffffffu, st.l1, off);
    }
    if (lane < 2) scr_ml[warp * 2 + lane] = make_float4(st.m0, st.l0, st.m1, st.l1);
    consumer_bar();
    float M0 = -INFINITY, M1 = -INFINITY, L0 = 0.f, L1 = 0.f;
    {
      float4 ml[kConsumerWarps];
#pragma unroll
      for (int w = 0; w < kConsumerWarps; ++w) {
        ml[w] = scr_ml[w * 2 + (t4 & 1)];
        M0 = fmaxf(M0, ml[w].x); M1 = fmaxf(M1, ml[w].z);
      }
#pragma unroll
      for (int w = 0; w < kConsumerWarps; ++w) {
        L0 += ml[w].y * ex2(ml[w].x - M0);
        L1 += ml[w].w * ex2(ml[w].z - M1);
      }
    }
    float f0 = 0.f, f1 = 0.f;
    if (t4 < 2) {
      f0 = ex2(st.m0 - M0); f1 = ex2(st.m1 - M1);
      if (!sg.partial) { f0 *= rcp(L0); f1 *= rcp(L1); }
      a0 *= f0; a1 *= f1;
      float2* dst = scr + warp * (kD * 2) + g * 2 + t4;
#pragma unroll
      for (int i = 0; i < 8; ++i) {
        dst[32 * i] = make_float2(st.o[i][0] * a0, st.o[i][1] * a1);
        dst[32 * i + 16] = make_float2(st.o[i][2] * a0, st.o[i][3] * a1);
      }
    }
    pfrag[warp * 32 + lane] = make_uint2(movmatrix_t(pack_bf16(p[0] * f0, p[1] * f1)),
                                         movmatrix_t(pack_bf16(p[2] * f0, p[3] * f1)));
    consumer_bar();
    float acc[4][4];
    uint2 pf[8];
    {
      float c0 = 0.f, c1 = 0.f, c2 = 0.f, c3 = 0.f;
      const float2* src = scr + (16 * warp + g) * 2 + (t4 & 1);
#pragma unroll
      for (int w = 0; w < kConsumerWarps; ++w) {
        const float2 u = src[w * (kD * 2)], v = src[w * (kD * 2) + 16];
        c0 += u.x; c1 += u.y; c2 += v.x; c3 += v.y;
        pf[w] = pfrag[w * 32 + lane];
      }
      acc[0][0] = c0; acc[0][1] = c1; acc[0][2] = c2; acc[0][3] = c3;
#pragma unroll
      for (int j = 1; j < 4; ++j) acc[j][0] = acc[j][1] = acc[j][2] = acc[j][3] = 0.f;
    }
    {
      mbar_wait(bar_full + slot * 8, phase);
      const uint32_t base = sb + kOffRing + slot * kSlotBytes + voff_last;
      uint32_t a[8][4];
#pragma unroll
      for (int j = 0; j < 8; ++j) ldsm4t(a[j], base + j * 4096);
#pragma unroll
      for (int j = 0; j < 8; ++j) mma16816(acc[j & 3], a[j], pf[j].x, pf[j].y);
      __syncwarp();
      if (lane == 0) mbar_arrive(bar_empty + slot * 8);
      if (++slot == kSlots) { slot = 0; phase ^= 1; }
    }
    float o[4];
#pragma unroll
    for (int i = 0; i < 4; ++i) o[i] = (acc[0][i] + acc[1][i]) + (acc[2][i] + acc[3][i]);
    if (!sg.partial) {
      const uint32_t w0 = movmatrix_t(pack_bf16(o[0], o[1]));
      const uint32_t w1 = __shfl_xor_sync(0xffffffffu, movmatrix_t(pack_bf16(o[2], o[3])), 16);
      *reinterpret_cast<uint32_t*>(out + ((size_t)sg.head * kT + (g & 3)) * kD + 16 * warp + (g >> 2) * 8 + 2 * t4) =
          lane < 16 ? w0 : w1;
    } else {
      float* part = reinterpret_cast<float*>(sp + kOffPart + s * kPartBytes);
      if (t4 < 2) {
        float* row = part + 2 * t4 * kD + 16 * warp + g;
        row[0] = o[0]; row[kD] = o[1]; row[8] = o[2]; row[kD + 8] = o[3];
        if (warp == 0 && g == 0) {
          part[kT * kD + 2 * t4] = M0; part[kT * kD + 2 * t4 + 1] = M1;
          part[kT * kD + kT + 2 * t4] = L0; part[kT * kD + kT + 2 * t4 + 1] = L1;
        }
      }
      __syncwarp();
      if (lane == 0) mbar_arrive(bar_part + s * 8);
    }
  }
}

typedef CUresult (*EncodeTiledFn)(CUtensorMap*, CUtensorMapDataType, cuuint32_t, void*, const cuuint64_t*,
                                  const cuuint64_t*, const cuuint32_t*, const cuuint32_t*, CUtensorMapInterleave,
                                  CUtensorMapSwizzle, CUtensorMapL2promotion, CUtensorMapFloatOOBfill);

bool make_map(EncodeTiledFn enc, CUtensorMap* m, void* base) {
  const cuuint64_t rows = (cuuint64_t)kNH * kC;
  cuuint64_t dims[4] = {64, 8, 2, rows / 8};
  cuuint64_t strides[3] = {256, 128, 2048};
  cuuint32_t box[4] = {64, 8, 2, kTileKeys / 8};
  cuuint32_t es[4] = {1, 1, 1, 1};
  return enc(m, CU_TENSOR_MAP_DATA_TYPE_BFLOAT16, 4, base, dims, strides, box, es, CU_TENSOR_MAP_INTERLEAVE_NONE,
             CU_TENSOR_MAP_SWIZZLE_128B, CU_TENSOR_MAP_L2_PROMOTION_NONE,
             CU_TENSOR_MAP_FLOAT_OOB_FILL_NONE) == CUDA_SUCCESS;
}

constexpr int kH100Sms = 132;

}

extern "C" void kernel_launch(void* const* d_in, const int* in_sizes, int n_in, void* d_out, int out_size) {
  (void)in_sizes; (void)n_in; (void)out_size;
  static EncodeTiledFn enc = nullptr;
  static int grid = 0;
  if (!enc) {
    void* fn = nullptr;
    cudaDriverEntryPointQueryResult qr;
    cudaGetDriverEntryPoint("cuTensorMapEncodeTiled", &fn, cudaEnableDefault, &qr);
    enc = (EncodeTiledFn)fn;
    int dev = 0, sms = 0;
    cudaGetDevice(&dev);
    cudaDeviceGetAttribute(&sms, cudaDevAttrMultiProcessorCount, dev);
    grid = sms < kMaxCtas ? sms : kMaxCtas;
    cudaFuncSetAttribute(tree_attn_kernel<kH100Sms>, cudaFuncAttributeMaxDynamicSharedMemorySize, kSmemBytes);
    cudaFuncSetAttribute(tree_attn_kernel<0>, cudaFuncAttributeMaxDynamicSharedMemorySize, kSmemBytes);
  }
  CUtensorMap map_k, map_v;
  if (!enc || !make_map(enc, &map_k, d_in[1]) || !make_map(enc, &map_v, d_in[2])) return;
  auto* kernel = grid == kH100Sms ? tree_attn_kernel<kH100Sms> : tree_attn_kernel<0>;
  kernel<<<grid, kThreads, kSmemBytes, cudaStreamPerThread>>>(
      map_k, map_v, (const __nv_bfloat16*)d_in[0], (const __nv_bfloat16*)d_in[3], (const __nv_bfloat16*)d_in[4],
      (const __nv_bfloat16*)d_in[5], (__nv_bfloat16*)d_out);
}
```

```cpp
#include <cuda_runtime.h>
#include <cuda_bf16.h>
#include <cuda.h>
#include <stdint.h>

namespace {

constexpr int kHeadsPerBatch = 32;
constexpr int kNH = 512;
constexpr int kT = 4;
constexpr int kC = 2048;
constexpr int kD = 128;
constexpr int kTileKeys = 128;
constexpr int kTPH = kC / (2 * kTileKeys);
constexpr int kTotalTiles = kNH * kTPH * 4;
constexpr int kSlots = 6;
constexpr int kPaceStart = kSlots;
constexpr float kPaceLead = 0.35f;
constexpr int kSlotBytes = kTileKeys * kD * 2;
constexpr int kConsumerWarps = 8;
constexpr int kConsumerThreads = kConsumerWarps * 32;
constexpr int kProducerWarp = kConsumerWarps;
constexpr int kFinalizerWarp = kConsumerWarps + 1;
constexpr int kPacerWarp = kConsumerWarps + 2;
constexpr int kThreads = kConsumerThreads + 96;
constexpr int kMaxCtas = 256;

constexpr int kSegBytes = 3200;

constexpr int kOffRing = 0;
constexpr int kOffSeg = kOffRing + kSlots * kSlotBytes;
constexpr int kOffScr = kOffSeg + 2 * kSegBytes;
constexpr int kOffPf = kOffScr + kConsumerWarps * kD * kT * 4;
constexpr int kOffML = kOffPf + 2 * kConsumerWarps * 32 * 8;
constexpr int kPartBytes = (kT * kD + 2 * kT) * 4;
constexpr int kOffPart = kOffML + kConsumerWarps * 2 * 16;
constexpr int kOffBar = kOffPart + 2 * kPartBytes;
constexpr int kOffPace = kOffBar + (2 * kSlots + 6) * 8;
constexpr int kSmemBytes = kOffPace + 8 + 1024;

constexpr float kScale = 0.08838834764831845f;
constexpr float kLog2e = 1.4426950408889634f;

struct __align__(16) Partial {
  float o[kT * kD];
  float m[kT];
  float l[kT];
};

__device__ Partial g_partial[kMaxCtas * 2];
__device__ unsigned g_count[kNH];
__device__ unsigned g_progress;

__device__ __forceinline__ uint32_t smem_u32(const void* p) { return (uint32_t)__cvta_generic_to_shared(p); }

__device__ __forceinline__ void mbar_init(uint32_t bar, uint32_t count) {
  asm volatile("mbarrier.init.shared::cta.b64 [%0], %1;" ::"r"(bar), "r"(count));
}
__device__ __forceinline__ void mbar_expect_tx(uint32_t bar, uint32_t bytes) {
  asm volatile("mbarrier.arrive.expect_tx.shared::cta.b64 _, [%0], %1;" ::"r"(bar), "r"(bytes) : "memory");
}
__device__ __forceinline__ void mbar_arrive(uint32_t bar) {
  asm volatile("mbarrier.arrive.shared::cta.b64 _, [%0];" ::"r"(bar) : "memory");
}
__device__ __forceinline__ bool mbar_try(uint32_t bar, uint32_t parity) {
  uint32_t ok;
  asm volatile("{\n.reg .pred P;\nmbarrier.try_wait.parity.shared::cta.b64 P, [%1], %2;\nselp.u32 %0, 1, 0, P;\n}"
               : "=r"(ok) : "r"(bar), "r"(parity) : "memory");
  return ok != 0;
}
__device__ __forceinline__ void mbar_wait(uint32_t bar, uint32_t parity) {
  if (mbar_try(bar, parity)) return;
  for (uint32_t spin = 0; !mbar_try(bar, parity); ++spin)
    if (spin > (1u << 24)) __trap();
}
__device__ __forceinline__ void bulk_load(uint32_t dst, const void* src, uint32_t bytes, uint32_t bar) {
  asm volatile("cp.async.bulk.shared::cluster.global.mbarrier::complete_tx::bytes [%0], [%1], %2, [%3];"
               ::"r"(dst), "l"(src), "r"(bytes), "r"(bar) : "memory");
}
__device__ __forceinline__ void tma_tile(uint32_t dst, const CUtensorMap* map, int row8, uint32_t bar, uint64_t policy) {
  asm volatile("cp.async.bulk.tensor.4d.shared::cluster.global.mbarrier::complete_tx::bytes.L2::cache_hint"
               " [%0], [%1, {%3,%3,%3,%4}], [%2], %5;"
               ::"r"(dst), "l"(map), "r"(bar), "r"(0), "r"(row8), "l"(policy) : "memory");
}
__device__ __forceinline__ void ldsm4(uint32_t (&r)[4], uint32_t addr) {
  asm volatile("ldmatrix.sync.aligned.m8n8.x4.shared.b16 {%0,%1,%2,%3}, [%4];"
               : "=r"(r[0]), "=r"(r[1]), "=r"(r[2]), "=r"(r[3]) : "r"(addr) : "memory");
}
__device__ __forceinline__ void ldsm4t(uint32_t (&r)[4], uint32_t addr) {
  asm volatile("ldmatrix.sync.aligned.m8n8.x4.trans.shared.b16 {%0,%1,%2,%3}, [%4];"
               : "=r"(r[0]), "=r"(r[1]), "=r"(r[2]), "=r"(r[3]) : "r"(addr) : "memory");
}
__device__ __forceinline__ void mma16816(float (&c)[4], const uint32_t (&a)[4], uint32_t b0, uint32_t b1) {
  asm volatile("mma.sync.aligned.m16n8k16.row.col.f32.bf16.bf16.f32 {%0,%1,%2,%3}, {%4,%5,%6,%7}, {%8,%9}, {%0,%1,%2,%3};"
               : "+f"(c[0]), "+f"(c[1]), "+f"(c[2]), "+f"(c[3])
               : "r"(a[0]), "r"(a[1]), "r"(a[2]), "r"(a[3]), "r"(b0), "r"(b1));
}
__device__ __forceinline__ uint32_t movmatrix_t(uint32_t x) {
  uint32_t y;
  asm volatile("movmatrix.sync.aligned.m8n8.trans.b16 %0, %1;" : "=r"(y) : "r"(x));
  return y;
}
__device__ __forceinline__ float ex2(float x) {
  float y;
  asm("ex2.approx.ftz.f32 %0, %1;" : "=f"(y) : "f"(x));
  return y;
}
__device__ __forceinline__ float rcp(float x) {
  float y;
  asm("rcp.approx.ftz.f32 %0, %1;" : "=f"(y) : "f"(x));
  return y;
}
__device__ __forceinline__ uint32_t pack_bf16(float lo, float hi) {
  uint32_t y;
  asm("cvt.rn.bf16x2.f32 %0, %1, %2;" : "=r"(y) : "f"(hi), "f"(lo));
  return y;
}
__device__ __forceinline__ void consumer_bar() { asm volatile("bar.sync 1, 256;" ::: "memory"); }

struct WarpState {
  float o[8][4];
  float m0, m1, l0, l1;
};

template <int N>
__device__ __forceinline__ void softmax_update(WarpState& st, const float (&x)[N], float (&p)[N], float& a0, float& a1) {
  float mx0 = x[0], mx1 = x[1];
#pragma unroll
  for (int i = 2; i < N; i += 2) { mx0 = fmaxf(mx0, x[i]); mx1 = fmaxf(mx1, x[i + 1]); }
#pragma unroll
  for (int off = 4; off < 32; off <<= 1) {
    mx0 = fmaxf(mx0, __shfl_xor_sync(0xffffffffu, mx0, off));
    mx1 = fmaxf(mx1, __shfl_xor_sync(0xffffffffu, mx1, off));
  }
  const float mn0 = fmaxf(st.m0, mx0), mn1 = fmaxf(st.m1, mx1);
  a0 = ex2(st.m0 - mn0); a1 = ex2(st.m1 - mn1);
  float s0 = 0.f, s1 = 0.f;
#pragma unroll
  for (int i = 0; i < N; i += 2) {
    p[i] = ex2(x[i] - mn0); p[i + 1] = ex2(x[i + 1] - mn1);
    s0 += p[i]; s1 += p[i + 1];
  }
  st.m0 = mn0; st.m1 = mn1;
  st.l0 = st.l0 * a0 + s0;
  st.l1 = st.l1 * a1 + s1;
}
template <int N>
__device__ __forceinline__ void softmax_step(WarpState& st, const float (&x)[N], uint32_t (&pb)[N / 2]) {
  float p[N], a0, a1;
  softmax_update<N>(st, x, p, a0, a1);
#pragma unroll
  for (int i = 0; i < 8; ++i) {
    st.o[i][0] *= a0; st.o[i][1] *= a1; st.o[i][2] *= a0; st.o[i][3] *= a1;
  }
#pragma unroll
  for (int i = 0; i < N / 2; ++i) pb[i] = movmatrix_t(pack_bf16(p[2 * i], p[2 * i + 1]));
}

struct Segment { int head, t0, t1; bool partial; };

struct Schedule {
  int c, grid, full, nrem, lo, hi, remT;
  __device__ Schedule(int c_, int grid_) : c(c_), grid(grid_) {
    full = kNH / grid;
    remT = (kNH - full * grid) * kTPH;
    lo = remT * c / grid;
    hi = remT * (c + 1) / grid;
    nrem = (hi > lo) ? ((hi - 1) / kTPH - lo / kTPH + 1) : 0;
  }
  __device__ int count() const { return nrem + full; }
  __device__ Segment get(int s) const {
    Segment g;
    if (s < nrem) {
      const int r = lo / kTPH + s;
      g.head = full * grid + r;
      g.t0 = max(lo - r * kTPH, 0);
      g.t1 = min(hi - r * kTPH, kTPH);
      g.partial = true;
    } else {
      g.head = c + (s - nrem) * grid;
      g.t0 = 0; g.t1 = kTPH; g.partial = false;
    }
    return g;
  }
};

template <int kGrid>
__global__ void __launch_bounds__(kThreads, 1)
tree_attn_kernel(const __grid_constant__ CUtensorMap map_k, const __grid_constant__ CUtensorMap map_v,
                 const __nv_bfloat16* __restrict__ q, const __nv_bfloat16* __restrict__ k_tree,
                 const __nv_bfloat16* __restrict__ v_tree, const __nv_bfloat16* __restrict__ mask,
                 __nv_bfloat16* __restrict__ out, const uint8_t* __restrict__ k_raw) {
  extern __shared__ uint8_t smem_raw[];
  if (threadIdx.x == 0) {
    const int grid = kGrid ? kGrid : (int)gridDim.x;
    const int full = kNH / grid, rem = (kNH - full * grid) * kTPH;
    const int first = rem ? full * grid * kTPH + rem * (int)blockIdx.x / grid : (int)blockIdx.x * kTPH;
    uint64_t policy;
    asm volatile("createpolicy.fractional.L2::evict_first.b64 %0, 1.0;" : "=l"(policy));
    asm volatile("cp.async.bulk.prefetch.L2.global.L2::cache_hint [%0], %1, %2;"
                 ::"l"(k_raw + (size_t)first * (2 * kSlotBytes)), "n"(2 * kSlotBytes), "l"(policy) : "memory");
  }
  const uint32_t raw = smem_u32(smem_raw);
  const uint32_t sb = (raw + 1023u) & ~1023u;
  uint8_t* sp = smem_raw + (sb - raw);

  const uint32_t bar_full = sb + kOffBar;
  const uint32_t bar_empty = bar_full + kSlots * 8;
  const uint32_t bar_segfull = bar_empty + kSlots * 8;
  const uint32_t bar_segempty = bar_segfull + 16;
  const uint32_t bar_part = bar_segempty + 16;
  volatile uint32_t* s_pace = reinterpret_cast<volatile uint32_t*>(sp + kOffPace);

  const int warp = threadIdx.x >> 5, lane = threadIdx.x & 31;
  const Schedule sched(blockIdx.x, kGrid ? kGrid : (int)gridDim.x);
  const int nseg = sched.count();

  if (warp == kProducerWarp) {
    if (lane == 0) {
      asm volatile("prefetch.tensormap [%0];" ::"l"(&map_k) : "memory");
      asm volatile("prefetch.tensormap [%0];" ::"l"(&map_v) : "memory");
      for (int s = 0; s < kSlots; ++s) {
        mbar_init(bar_full + s * 8, 1);
        mbar_init(bar_empty + s * 8, kConsumerWarps);
      }
      for (int s = 0; s < 2; ++s) {
        mbar_init(bar_segfull + s * 8, 1);
        mbar_init(bar_segempty + s * 8, kConsumerWarps);
        mbar_init(bar_part + s * 8, kConsumerWarps);
      }
      s_pace[0] = 0;
      s_pace[1] = 0;
      asm volatile("fence.mbarrier_init.release.cluster;" ::: "memory");
      asm volatile("fence.proxy.async.shared::cta;" ::: "memory");
    }
    __syncwarp();
    asm volatile("bar.arrive 2, %0;" ::"n"(kThreads) : "memory");
    if (lane == 0) {
      uint64_t policy;
      asm volatile("createpolicy.fractional.L2::evict_first.b64 %0, 1.0;" : "=l"(policy));
      int slot = 0; uint32_t phase = 1;
      const int ntiles = ((sched.hi - sched.lo) + sched.full * kTPH) * 4;
      const float per = (float)kTotalTiles / (float)ntiles;
      int ti = 0; bool pace = true;
      for (int s = 0; s < nseg; ++s) {
        const Segment sg = sched.get(s);
        for (int t = sg.t0; t < sg.t1; ++t) {
          const int row8 = (sg.head * kC + t * (2 * kTileKeys)) >> 3;
#pragma unroll
          for (int j = 0; j < 4; ++j) {
            mbar_wait(bar_empty + slot * 8, phase);
            if (pace && ti >= kPaceStart) {
              const int need = (int)(((float)ti - kPaceLead) * per);
              for (int spin = 0; (int)s_pace[0] < need; ++spin)
                if (spin > 200000) { pace = false; break; }
            }
            mbar_expect_tx(bar_full + slot * 8, kSlotBytes);
            tma_tile(sb + kOffRing + slot * kSlotBytes, j < 2 ? &map_k : &map_v, row8 + (j & 1) * (kTileKeys / 8),
                     bar_full + slot * 8, policy);
            if (++slot == kSlots) { slot = 0; phase ^= 1; }
            asm volatile("red.relaxed.gpu.global.add.u32 [%0], 1;" ::"l"(&g_progress) : "memory");
            if (++ti == ntiles) s_pace[1] = 1;
            if (j == 0 && t == sg.t0) {
              const int buf = s & 1;
              const uint32_t sbuf = sb + kOffSeg + buf * kSegBytes;
              const uint32_t bar = bar_segfull + buf * 8;
              const bool tree = sg.t1 == kTPH;
              mbar_wait(bar_segempty + buf * 8, ((s >> 1) & 1) ^ 1);
              mbar_expect_tx(bar, tree ? 3 * 1024 + 32 : 1024);
              bulk_load(sbuf, q + (size_t)sg.head * (kT * kD), 1024, bar);
              if (tree) {
                bulk_load(sbuf + 1024, k_tree + (size_t)sg.head * (kT * kD), 1024, bar);
                bulk_load(sbuf + 2048, v_tree + (size_t)sg.head * (kT * kD), 1024, bar);
                bulk_load(sbuf + 3072, mask + (size_t)(sg.head / kHeadsPerBatch) * (kT * kT), 32, bar);
              }
            }
          }
        }
      }
    }
    return;
  }
  asm volatile("bar.sync 2, %0;" ::"n"(kThreads) : "memory");

  if (warp == kPacerWarp) {
    if (lane == 0) {
      unsigned base = 0;
      for (int spin = 0; spin < (1 << 22); ++spin) {
        unsigned v;
        asm volatile("ld.relaxed.gpu.global.u32 %0, [%1];" : "=r"(v) : "l"(&g_progress) : "memory");
        if (spin == 0) base = v & ~(unsigned)(kTotalTiles - 1);
        s_pace[0] = v - base;
        if (s_pace[1]) break;
      }
    }
    return;
  }

  if (warp == kFinalizerWarp) {
    for (int s = 0; s < sched.nrem; ++s) {
      const Segment sg = sched.get(s);
      mbar_wait(bar_part + s * 8, 0);
      const float4* src = reinterpret_cast<const float4*>(sp + kOffPart + s * kPartBytes);
      float4* dst = reinterpret_cast<float4*>(&g_partial[blockIdx.x * 2 + s]);
#pragma unroll
      for (int i = 0; i < kT; ++i) __stcg(dst + lane + 32 * i, src[lane + 32 * i]);
      if (lane < 2) __stcg(dst + 128 + lane, src[128 + lane]);
      __threadfence();
      __syncwarp();
      unsigned last = 0;
      if (lane == 0) {
        const unsigned n = sg.t1 - sg.t0;
        last = atomicAdd(&g_count[sg.head], n) + n == kTPH;
        if (last) g_count[sg.head] = 0;
      }
      last = __shfl_sync(0xffffffffu, last, 0);
      if (last) {
        __threadfence();
        const int x0 = (sg.head - sched.full * sched.grid) * kTPH;
        const int c_lo = ((x0 + 1) * sched.grid - 1) / sched.remT;
        const int c_hi = ((x0 + kTPH) * sched.grid - 1) / sched.remT;
        float M[kT], L[kT];
        float4 O[kT];
#pragma unroll
        for (int i = 0; i < kT; ++i) { M[i] = -INFINITY; L[i] = 0.f; O[i] = make_float4(0.f, 0.f, 0.f, 0.f); }
        for (int c = c_lo; c <= c_hi; ++c) {
          const int lo = sched.remT * c / sched.grid, hi = sched.remT * (c + 1) / sched.grid;
          if (hi <= lo) continue;
          const float4* pp = reinterpret_cast<const float4*>(&g_partial[c * 2 + (lo < x0 ? 1 : 0)]);
          const float4 pm4 = __ldcg(pp + 128), pl4 = __ldcg(pp + 129);
          const float pm[kT] = {pm4.x, pm4.y, pm4.z, pm4.w}, pl[kT] = {pl4.x, pl4.y, pl4.z, pl4.w};
#pragma unroll
          for (int i = 0; i < kT; ++i) {
            const float4 v = __ldcg(pp + lane + 32 * i);
            const float mn = fmaxf(M[i], pm[i]);
            const float a = ex2(M[i] - mn), b = ex2(pm[i] - mn);
            L[i] = L[i] * a + pl[i] * b;
            O[i].x = O[i].x * a + v.x * b; O[i].y = O[i].y * a + v.y * b;
            O[i].z = O[i].z * a + v.z * b; O[i].w = O[i].w * a + v.w * b;
            M[i] = mn;
          }
        }
#pragma unroll
        for (int i = 0; i < kT; ++i) {
          const float inv = 1.0f / L[i];
          *reinterpret_cast<uint2*>(out + ((size_t)sg.head * kT + i) * kD + 4 * lane) =
              make_uint2(pack_bf16(O[i].x * inv, O[i].y * inv), pack_bf16(O[i].z * inv, O[i].w * inv));
        }
      }
    }
    return;
  }

  const int g = lane >> 2, t4 = lane & 3;
  const int mi = lane >> 3, r = lane & 7;
  const uint32_t koff = (2 * warp + (mi & 1)) * 2048 + r * 128;
  const uint32_t kxor = ((mi >> 1) ^ r) << 4;
  const uint32_t voff = (2 * warp + (mi >> 1)) * 2048 + r * 128;
  const uint32_t vxor = ((mi & 1) ^ r) << 4;
  const uint32_t voff_last = (mi >> 1) * 2048 + r * 128 + (warp >> 2) * 1024 + (vxor ^ ((warp & 3) << 5));

  float2* scr = reinterpret_cast<float2*>(sp + kOffScr);
  uint2* pfrag = reinterpret_cast<uint2*>(sp + kOffPf);
  float4* scr_ml = reinterpret_cast<float4*>(sp + kOffML);

  int slot = 0; uint32_t phase = 0;
  for (int s = 0; s < nseg; ++s) {
    const Segment sg = sched.get(s);
    const int buf = s & 1;
    const uint32_t sbuf = sb + kOffSeg + buf * kSegBytes;
    mbar_wait(bar_segfull + buf * 8, (s >> 1) & 1);

    uint32_t qf[8][2];
    {
      const uint32_t* qs = reinterpret_cast<const uint32_t*>(sp + kOffSeg + buf * kSegBytes);
#pragma unroll
      for (int kk = 0; kk < 8; ++kk) {
        qf[kk][0] = (g < kT) ? qs[(g & 3) * 64 + kk * 8 + t4] : 0u;
        qf[kk][1] = (g < kT) ? qs[(g & 3) * 64 + kk * 8 + 4 + t4] : 0u;
      }
    }

    WarpState st;
#pragma unroll
    for (int i = 0; i < 8; ++i) { st.o[i][0] = st.o[i][1] = st.o[i][2] = st.o[i][3] = 0.f; }
    st.m0 = st.m1 = -INFINITY;
    st.l0 = st.l1 = 0.f;

    if (sg.t1 == kTPH && warp == 0) {
      float c[4] = {0.f, 0.f, 0.f, 0.f};
      const uint32_t ka = sbuf + 1024 + (r & 3) * 256 + (mi >> 1) * 16;
#pragma unroll
      for (int kk = 0; kk < 8; ++kk) {
        uint32_t a[4];
        ldsm4(a, ka + kk * 32);
        mma16816(c, a, qf[kk][0], qf[kk][1]);
      }
      const __nv_bfloat16* ms = reinterpret_cast<const __nv_bfloat16*>(sp + kOffSeg + buf * kSegBytes + 3072);
      const int q0 = (2 * t4) & 3;
      const float mk0 = __bfloat162float(ms[q0 * kT + (g & 3)]);
      const float mk1 = __bfloat162float(ms[(q0 + 1) * kT + (g & 3)]);
      float x[4];
      x[0] = (g < kT) ? fmaf(c[0], kScale, (1.0f - mk0) * -1000000000.0f) * kLog2e : -INFINITY;
      x[1] = (g < kT) ? fmaf(c[1], kScale, (1.0f - mk1) * -1000000000.0f) * kLog2e : -INFINITY;
      x[2] = -INFINITY;
      x[3] = -INFINITY;
      uint32_t pb[2];
      softmax_step<4>(st, x, pb);
      const uint32_t va = sbuf + 2048 + (r & 3) * 256 + (mi & 1) * 16;
#pragma unroll
      for (int i = 0; i < 8; ++i) {
        uint32_t a[4];
        ldsm4t(a, va + i * 32);
        mma16816(st.o[i], a, pb[0], pb[1]);
      }
    }
    __syncwarp();
    if (lane == 0) mbar_arrive(bar_segempty + buf * 8);

    auto scores = [&](float* x) {
      mbar_wait(bar_full + slot * 8, phase);
      const uint32_t base = sb + kOffRing + slot * kSlotBytes + koff;
      float ca[4] = {0.f, 0.f, 0.f, 0.f}, cb[4] = {0.f, 0.f, 0.f, 0.f};
      uint32_t a[8][4];
#pragma unroll
      for (int kk = 0; kk < 8; ++kk) ldsm4(a[kk], base + (kk >> 2) * 1024 + (kxor ^ ((kk & 3) << 5)));
#pragma unroll
      for (int kk = 0; kk < 8; kk += 2) {
        mma16816(ca, a[kk], qf[kk][0], qf[kk][1]);
        mma16816(cb, a[kk + 1], qf[kk + 1][0], qf[kk + 1][1]);
      }
      __syncwarp();
      if (lane == 0) mbar_arrive(bar_empty + slot * 8);
      if (++slot == kSlots) { slot = 0; phase ^= 1; }
      const float sc = kScale * kLog2e;
#pragma unroll
      for (int i = 0; i < 4; ++i) x[i] = (ca[i] + cb[i]) * sc;
    };

    for (int t = sg.t0; t + 1 < sg.t1; ++t) {
      float x[8];
      uint32_t pb[4];
      scores(x);
      scores(x + 4);
      softmax_step<8>(st, x, pb);
#pragma unroll
      for (int j = 0; j < 2; ++j) {
        mbar_wait(bar_full + slot * 8, phase);
        const uint32_t base = sb + kOffRing + slot * kSlotBytes + voff;
        uint32_t a[8][4];
#pragma unroll
        for (int i = 0; i < 8; ++i) ldsm4t(a[i], base + (i >> 2) * 1024 + (vxor ^ ((i & 3) << 5)));
#pragma unroll
        for (int i = 0; i < 8; ++i) mma16816(st.o[i], a[i], pb[2 * j], pb[2 * j + 1]);
        __syncwarp();
        if (lane == 0) mbar_arrive(bar_empty + slot * 8);
        if (++slot == kSlots) { slot = 0; phase ^= 1; }
      }
    }

    float x[8], p[8], a0, a1;
    scores(x);
    scores(x + 4);
    softmax_update<8>(st, x, p, a0, a1);
#pragma unroll
    for (int off = 4; off < 32; off <<= 1) {
      st.l0 += __shfl_xor_sync(0xffffffffu, st.l0, off);
      st.l1 += __shfl_xor_sync(0xffffffffu, st.l1, off);
    }
    if (lane < 2) scr_ml[warp * 2 + lane] = make_float4(st.m0, st.l0, st.m1, st.l1);
    consumer_bar();
    float M0 = -INFINITY, M1 = -INFINITY, L0 = 0.f, L1 = 0.f;
    {
      float4 ml[kConsumerWarps];
#pragma unroll
      for (int w = 0; w < kConsumerWarps; ++w) {
        ml[w] = scr_ml[w * 2 + (t4 & 1)];
        M0 = fmaxf(M0, ml[w].x); M1 = fmaxf(M1, ml[w].z);
      }
#pragma unroll
      for (int w = 0; w < kConsumerWarps; ++w) {
        L0 += ml[w].y * ex2(ml[w].x - M0);
        L1 += ml[w].w * ex2(ml[w].z - M1);
      }
    }
    float f0 = 0.f, f1 = 0.f;
    if (t4 < 2) {
      f0 = ex2(st.m0 - M0); f1 = ex2(st.m1 - M1);
      if (!sg.partial) { f0 *= rcp(L0); f1 *= rcp(L1); }
      a0 *= f0; a1 *= f1;
      float2* dst = scr + warp * (kD * 2) + g * 2 + t4;
#pragma unroll
      for (int i = 0; i < 8; ++i) {
        dst[32 * i] = make_float2(st.o[i][0] * a0, st.o[i][1] * a1);
        dst[32 * i + 16] = make_float2(st.o[i][2] * a0, st.o[i][3] * a1);
      }
    }
#pragma unroll
    for (int j = 0; j < 2; ++j)
      pfrag[(j * kConsumerWarps + warp) * 32 + lane] =
          make_uint2(movmatrix_t(pack_bf16(p[4 * j] * f0, p[4 * j + 1] * f1)),
                     movmatrix_t(pack_bf16(p[4 * j + 2] * f0, p[4 * j + 3] * f1)));
    consumer_bar();
    float acc[4][4];
    uint2 pf[2][8];
    {
      float c0 = 0.f, c1 = 0.f, c2 = 0.f, c3 = 0.f;
      const float2* src = scr + (16 * warp + g) * 2 + (t4 & 1);
#pragma unroll
      for (int w = 0; w < kConsumerWarps; ++w) {
        const float2 u = src[w * (kD * 2)], v = src[w * (kD * 2) + 16];
        c0 += u.x; c1 += u.y; c2 += v.x; c3 += v.y;
        pf[0][w] = pfrag[w * 32 + lane];
        pf[1][w] = pfrag[(kConsumerWarps + w) * 32 + lane];
      }
      acc[0][0] = c0; acc[0][1] = c1; acc[0][2] = c2; acc[0][3] = c3;
#pragma unroll
      for (int j = 1; j < 4; ++j) acc[j][0] = acc[j][1] = acc[j][2] = acc[j][3] = 0.f;
    }
#pragma unroll
    for (int k = 0; k < 2; ++k) {
      mbar_wait(bar_full + slot * 8, phase);
      const uint32_t base = sb + kOffRing + slot * kSlotBytes + voff_last;
      uint32_t a[8][4];
#pragma unroll
      for (int j = 0; j < 8; ++j) ldsm4t(a[j], base + j * 4096);
#pragma unroll
      for (int j = 0; j < 8; ++j) mma16816(acc[j & 3], a[j], pf[k][j].x, pf[k][j].y);
      __syncwarp();
      if (lane == 0) mbar_arrive(bar_empty + slot * 8);
      if (++slot == kSlots) { slot = 0; phase ^= 1; }
    }
    float o[4];
#pragma unroll
    for (int i = 0; i < 4; ++i) o[i] = (acc[0][i] + acc[1][i]) + (acc[2][i] + acc[3][i]);
    if (!sg.partial) {
      const uint32_t w0 = movmatrix_t(pack_bf16(o[0], o[1]));
      const uint32_t w1 = __shfl_xor_sync(0xffffffffu, movmatrix_t(pack_bf16(o[2], o[3])), 16);
      *reinterpret_cast<uint32_t*>(out + ((size_t)sg.head * kT + (g & 3)) * kD + 16 * warp + (g >> 2) * 8 + 2 * t4) =
          lane < 16 ? w0 : w1;
    } else {
      float* part = reinterpret_cast<float*>(sp + kOffPart + s * kPartBytes);
      if (t4 < 2) {
        float* row = part + 2 * t4 * kD + 16 * warp + g;
        row[0] = o[0]; row[kD] = o[1]; row[8] = o[2]; row[kD + 8] = o[3];
        if (warp == 0 && g == 0) {
          part[kT * kD + 2 * t4] = M0; part[kT * kD + 2 * t4 + 1] = M1;
          part[kT * kD + kT + 2 * t4] = L0; part[kT * kD + kT + 2 * t4 + 1] = L1;
        }
      }
      __syncwarp();
      if (lane == 0) mbar_arrive(bar_part + s * 8);
    }
  }
}

typedef CUresult (*EncodeTiledFn)(CUtensorMap*, CUtensorMapDataType, cuuint32_t, void*, const cuuint64_t*,
                                  const cuuint64_t*, const cuuint32_t*, const cuuint32_t*, CUtensorMapInterleave,
                                  CUtensorMapSwizzle, CUtensorMapL2promotion, CUtensorMapFloatOOBfill);

bool make_map(EncodeTiledFn enc, CUtensorMap* m, void* base) {
  const cuuint64_t rows = (cuuint64_t)kNH * kC;
  cuuint64_t dims[4] = {64, 8, 2, rows / 8};
  cuuint64_t strides[3] = {256, 128, 2048};
  cuuint32_t box[4] = {64, 8, 2, kTileKeys / 8};
  cuuint32_t es[4] = {1, 1, 1, 1};
  return enc(m, CU_TENSOR_MAP_DATA_TYPE_BFLOAT16, 4, base, dims, strides, box, es, CU_TENSOR_MAP_INTERLEAVE_NONE,
             CU_TENSOR_MAP_SWIZZLE_128B, CU_TENSOR_MAP_L2_PROMOTION_NONE,
             CU_TENSOR_MAP_FLOAT_OOB_FILL_NONE) == CUDA_SUCCESS;
}

constexpr int kH100Sms = 132;

}

extern "C" void kernel_launch(void* const* d_in, const int* in_sizes, int n_in, void* d_out, int out_size) {
  (void)in_sizes; (void)n_in; (void)out_size;
  static EncodeTiledFn enc = nullptr;
  static int grid = 0;
  if (!enc) {
    void* fn = nullptr;
    cudaDriverEntryPointQueryResult qr;
    cudaGetDriverEntryPoint("cuTensorMapEncodeTiled", &fn, cudaEnableDefault, &qr);
    enc = (EncodeTiledFn)fn;
    int dev = 0, sms = 0;
    cudaGetDevice(&dev);
    cudaDeviceGetAttribute(&sms, cudaDevAttrMultiProcessorCount, dev);
    grid = sms < kMaxCtas ? sms : kMaxCtas;
    cudaFuncSetAttribute(tree_attn_kernel<kH100Sms>, cudaFuncAttributeMaxDynamicSharedMemorySize, kSmemBytes);
    cudaFuncSetAttribute(tree_attn_kernel<0>, cudaFuncAttributeMaxDynamicSharedMemorySize, kSmemBytes);
  }
  CUtensorMap map_k, map_v;
  if (!enc || !make_map(enc, &map_k, d_in[1]) || !make_map(enc, &map_v, d_in[2])) return;
  auto* kernel = grid == kH100Sms ? tree_attn_kernel<kH100Sms> : tree_attn_kernel<0>;
  kernel<<<grid, kThreads, kSmemBytes, cudaStreamPerThread>>>(
      map_k, map_v, (const __nv_bfloat16*)d_in[0], (const __nv_bfloat16*)d_in[3], (const __nv_bfloat16*)d_in[4],
      (const __nv_bfloat16*)d_in[5], (__nv_bfloat16*)d_out, (const uint8_t*)d_in[1]);
}
```
